```python
import torch

def _softmax(x, axis=-1):
    return torch.softmax(x, dim=axis)
def _gelu(x):
    return torch.nn.functional.gelu(x, approximate="tanh")
def _silu(x):
    return torch.nn.functional.silu(x)
def _sigmoid(x):
    return torch.sigmoid(x)
def _layernorm(x, axis=-1, eps=1e-5):
    m = x.mean(dim=axis, keepdim=True)
    v = x.var(dim=axis, keepdim=True, unbiased=False)
    return (x - m) / torch.sqrt(v + eps)
def _scatter_add(tgt, idx, src, axis=0):
    return tgt.clone().index_add_(axis, idx, src)
def _segment_sum(src, seg, n):
    out = torch.zeros((n,) + src.shape[1:], dtype=src.dtype)
    return out.index_add_(0, seg, src)
def _pad(x, pw):
    flat = tuple(v for pair in reversed(pw) for v in pair)
    return torch.nn.functional.pad(x, flat)

kernel_name = 'interleave_layers__ssm_conv_h3__dense_activation_silu__prompt'

def setup_inputs():

    _w = (lambda a: (lambda t: t.to(torch.bfloat16) if t.is_floating_point() else t)(torch.as_tensor(a)))
    def _A_setup():
        B, S, D = 1, 2048, 448
        ks = 4
        return {
            "q": _w((lambda *s: torch.randn(*s, dtype=torch.bfloat16) * 0.05)(B, S, D)),
            "k": _w((lambda *s: torch.randn(*s, dtype=torch.bfloat16) * 0.2)(B, S, D)),
            "v": _w((lambda *s: torch.randn(*s, dtype=torch.bfloat16) * 0.2)(B, S, D)),
            "shift_k": _w((lambda *s: torch.randn(*s, dtype=torch.bfloat16) * 0.2)(D, ks) * 0.5),
            "ssm_k": _w((lambda *s: torch.randn(*s, dtype=torch.bfloat16) * 0.4)(D, S) * (1.0 / S ** 0.5)),
            "ssm_D": _w((lambda *s: torch.randn(*s, dtype=torch.bfloat16) * 0.2)(D)),
        }
    _A_in = _A_setup()

    def _B_setup():
        B, S, D, F = 1, 2048, 448, 1792
        return {
            "x": _w((lambda *s: torch.randn(*s, dtype=torch.bfloat16) * 0.05)(B, S, D)),
            "w1": _w((lambda *s: torch.randn(*s, dtype=torch.bfloat16) * 0.4)(D, F) * (D ** -0.5)),
            "w2": _w((lambda *s: torch.randn(*s, dtype=torch.bfloat16) * 0.1)(F, D) * (F ** -0.5)),
        }
    _B_in = _B_setup()

    return {
        "A_q": _A_in["q"],
        "A_k": _A_in["k"],
        "A_v": _A_in["v"],
        "A_shift_k": _A_in["shift_k"],
        "A_ssm_k": _A_in["ssm_k"],
        "A_ssm_D": _A_in["ssm_D"],
        "B_x": _B_in["x"],
        "B_w1": _B_in["w1"],
        "B_w2": _B_in["w2"],
    }

def reference(A_q, A_k, A_v, A_shift_k, A_ssm_k, A_ssm_D, B_x, B_w1, B_w2):
    def _A_ref(q, k, v, shift_k, ssm_k, ssm_D):
        B, S, D = q.shape
        ks = shift_k.shape[-1]
        k_pad = _pad(k, ((0, 0), (ks - 1, 0), (0, 0)))
        k_shift = torch.zeros_like(k)
        for t in range(ks):
            k_shift = k_shift + k_pad[:, t:t + S, :] * shift_k[:, ks - 1 - t][None, None, :]
        kv = k_shift * v
        L = 2 * S
        kv_pad = _pad(kv, ((0, 0), (0, S), (0, 0)))
        kf_pad = _pad(ssm_k, ((0, 0), (0, S)))
        kv_f = (lambda x, axes=(-2,-1): torch.fft.rfft2(x.float(), dim=axes))(kv_pad[:, None, :, :], axes=(1, 2))
        kf_f = (lambda x, axes=(-2,-1): torch.fft.rfft2(x.float(), dim=axes))(kf_pad[:, None, :], axes=(1, 2))
        kf_f = (lambda x, *d: x.permute(*d))(kf_f, 1, 2, 0)
        y_f = kv_f * kf_f[None, :, :, :]
        y = (lambda x, s, axes=(-2,-1): torch.fft.irfft2(x, s=s, dim=axes).to(torch.bfloat16))(y_f, (1, L), axes=(1, 2))[:, 0, :S, :]
        y = y + kv * ssm_D[None, None, :]
        return q * y

    def _B_ref(x, w1, w2):
        h = torch.einsum("bsd,df->bsf", x, w1)
        h = _silu(h)
        out = torch.einsum("bsf,fd->bsd", h, w2)
        return out

    x = A_q
    x = x + _A_ref(_layernorm(x, axis=-1), A_k, A_v, A_shift_k, A_ssm_k, A_ssm_D)
    x = x + _B_ref(_layernorm(x, axis=-1), B_w1, B_w2)
    x = x + _A_ref(_layernorm(x, axis=-1), A_k, A_v, A_shift_k, A_ssm_k, A_ssm_D)
    x = x + _B_ref(_layernorm(x, axis=-1), B_w1, B_w2)
    return x
```

```cpp
#include <cuda_runtime.h>
#include <cuda_bf16.h>
#include <cuda.h>
#include <stdint.h>

namespace {

constexpr int S_ = 2048, D_ = 448, F_ = 1792;
constexpr int SLOT = 28672, HSLOT = 14336, NSLOT = 7;
constexpr int SM_H = NSLOT * SLOT;
constexpr int SM_RED = SM_H + SLOT;
constexpr int SM_BAR = SM_RED + 1024;
constexpr int SM_TOTAL = SM_BAR + 2048;
#define DBGW 0
#define DBGSEL (wid * 128)
#define PVDELAY 8000
#define PWDELAY 5800
#define F0MIN 4050
#define S2DELAY 900
#define WGAP 450
#define WT 4900
#define WN 4
#define PLEADB 3100
#define PLEADA 3200
#define KLEAD 1050
#define HDELAY 2600
#define PQDELAY 4500
#define QDELAY 7050
#define WDELAY 9900
#define WSPACE 450
#define YALEAD 1850
#define X0LEADA 5750
#define YBLEAD 6300
#define X0LEADB 2550
#define XLEADA 6850
#define XLEADB 6400
#define PLEAD2 2750
#define SLEEPNS 64
#define AK 3
#define LDA1 4
constexpr uint32_t SPIN_LIMIT = 1u << 22;
#define SPIN_FAIL(line) __trap();

constexpr int REC = 6 * 7168, R_XN = 4 * 7168, R_YT = 5 * 7168;
constexpr int G_HK = 0;
constexpr int G_HY = 1024;
constexpr int G_FL = 2048;
constexpr int G_KV = 2048 + 16384, G_S = G_KV + 448 * 4096, G_TOTAL = G_S + 256 * REC;
__device__ __align__(1024) uint8_t g_scratch[G_TOTAL];
#define g_HK ((uint32_t*)(gs + G_HK))
#define g_HY ((uint32_t*)(gs + G_HY))
#define g_FL ((uint32_t*)(gs + G_FL))
#define g_KV (gs + G_KV)
#define g_S (gs + G_S)
constexpr int CV0 = 4 * SLOT, CV_P = CV0, PW_PITCH = 10368, CV_H = CV0 + 4 * PW_PITCH, H_PAD = 384, H_PITCH = 4096 + H_PAD,
              CV_S = CV_H + 4 * H_PITCH, SCR_W = 4352, CV_Q = CV_S + 8 * SCR_W,
              CV_T0 = CV_P, CV_T1 = CV_S;
#define STAMP(role, idx) do {} while (0)
#define CNT(role, idx, v) do {} while (0)

__device__ __forceinline__ uint32_t smem_u32(const void* p) { return (uint32_t)__cvta_generic_to_shared(p); }
__device__ __forceinline__ void mbar_init(uint32_t bar, uint32_t cnt) { asm volatile("mbarrier.init.shared::cta.b64 [%0], %1;" :: "r"(bar), "r"(cnt) : "memory"); }
__device__ __forceinline__ void mbar_expect_tx(uint32_t bar, uint32_t bytes) { asm volatile("mbarrier.arrive.expect_tx.shared::cta.b64 _, [%0], %1;" :: "r"(bar), "r"(bytes) : "memory"); }
__device__ __forceinline__ void mbar_expect_tx_e(uint32_t bar, uint32_t bytes) { asm volatile("{\n.reg .pred e;\nelect.sync _|e, -1;\n@e mbarrier.arrive.expect_tx.shared::cta.b64 _, [%0], %1;\n}" :: "r"(bar), "r"(bytes) : "memory"); }
__device__ __forceinline__ void mbar_arrive(uint32_t bar) { asm volatile("mbarrier.arrive.shared::cta.b64 _, [%0];" :: "r"(bar) : "memory"); }
__device__ __forceinline__ void mbar_arrive_remote(uint32_t bar) { asm volatile("mbarrier.arrive.shared::cluster.b64 _, [%0];" :: "r"(bar) : "memory"); }
__device__ __forceinline__ bool mbar_try(uint32_t bar, uint32_t parity) {
  uint32_t ok;
  asm volatile("{\n.reg .pred p;\nmbarrier.try_wait.parity.shared::cta.b64 p, [%1], %2;\nselp.u32 %0, 1, 0, p;\n}" : "=r"(ok) : "r"(bar), "r"(parity) : "memory");
  return ok;
}
#define mbar_wait(bar, parity) mbar_wait_(bar, parity, __LINE__)
__device__ __forceinline__ void mbar_wait_(uint32_t bar, uint32_t parity, int line) {
  uint32_t it = 0;
  #pragma unroll 1
  while (!mbar_try(bar, parity)) { if (++it > SPIN_LIMIT) SPIN_FAIL(line) }
}
__device__ __forceinline__ uint32_t mapa(uint32_t addr, uint32_t rank) { uint32_t r; asm volatile("mapa.shared::cluster.u32 %0, %1, %2;" : "=r"(r) : "r"(addr), "r"(rank)); return r; }
__device__ __forceinline__ void tma2d(uint32_t dst, const CUtensorMap* m, int c0, int c1, uint32_t bar) {
  asm volatile("{\n.reg .pred e;\nelect.sync _|e, -1;\n@e cp.async.bulk.tensor.2d.shared::cluster.global.mbarrier::complete_tx::bytes [%0], [%1, {%3, %4}], [%2];\n}"
    :: "r"(dst), "l"(m), "r"(bar), "r"(c0), "r"(c1) : "memory");
}
__device__ __forceinline__ void tma3d(uint32_t dst, const CUtensorMap* m, int c0, int c1, int c2, uint32_t bar) {
  asm volatile("{\n.reg .pred e;\nelect.sync _|e, -1;\n@e cp.async.bulk.tensor.3d.shared::cluster.global.mbarrier::complete_tx::bytes [%0], [%1, {%3, %4, %5}], [%2];\n}"
    :: "r"(dst), "l"(m), "r"(bar), "r"(c0), "r"(c1), "r"(c2) : "memory");
}
__device__ __forceinline__ void st_async128(uint32_t dst, uint32_t a, uint32_t b, uint32_t c, uint32_t d, uint32_t bar) {
  asm volatile("st.async.shared::cluster.mbarrier::complete_tx::bytes.v4.b32 [%0], {%1, %2, %3, %4}, [%5];"
    :: "r"(dst), "r"(a), "r"(b), "r"(c), "r"(d), "r"(bar) : "memory");
}
__device__ __forceinline__ void lds128(uint32_t* v, uint32_t a) {
  asm volatile("ld.shared.v4.b32 {%0, %1, %2, %3}, [%4];" : "=r"(v[0]), "=r"(v[1]), "=r"(v[2]), "=r"(v[3]) : "r"(a) : "memory");
}
__device__ __forceinline__ void bulk_g2s(uint32_t dst, const void* src, uint32_t bytes, uint32_t bar) {
  asm volatile("{\n.reg .pred e;\nelect.sync _|e, -1;\n@e cp.async.bulk.shared::cluster.global.mbarrier::complete_tx::bytes [%0], [%1], %2, [%3];\n}" :: "r"(dst), "l"(src), "r"(bytes), "r"(bar) : "memory");
}
__device__ __forceinline__ void pf(const void* p, uint32_t n) { asm volatile("{\n.reg .pred e;\nelect.sync _|e, -1;\n@e cp.async.bulk.prefetch.L2.global [%0], %1;\n}" :: "l"(p), "r"(n) : "memory"); }
__device__ __forceinline__ void cp_async16(uint32_t dst, const void* src, uint32_t bytes) {
  asm volatile("cp.async.cg.shared.global [%0], [%1], 16, %2;" :: "r"(dst), "l"(src), "r"(bytes) : "memory");
}
__device__ __forceinline__ void ldsm4t(uint32_t* v, uint32_t a) {
  asm volatile("ldmatrix.sync.aligned.m8n8.x4.trans.shared.b16 {%0, %1, %2, %3}, [%4];" : "=r"(v[0]), "=r"(v[1]), "=r"(v[2]), "=r"(v[3]) : "r"(a) : "memory");
}
__device__ __forceinline__ void ldsm4(uint32_t* v, uint32_t a) {
  asm volatile("ldmatrix.sync.aligned.m8n8.x4.shared.b16 {%0, %1, %2, %3}, [%4];" : "=r"(v[0]), "=r"(v[1]), "=r"(v[2]), "=r"(v[3]) : "r"(a) : "memory");
}
__device__ __forceinline__ void ldsm2(uint32_t* v, uint32_t a) {
  asm volatile("ldmatrix.sync.aligned.m8n8.x2.shared.b16 {%0, %1}, [%2];" : "=r"(v[0]), "=r"(v[1]) : "r"(a) : "memory");
}
__device__ __forceinline__ uint32_t lds32(uint32_t a) { uint32_t v; asm volatile("ld.shared.b32 %0, [%1];" : "=r"(v) : "r"(a) : "memory"); return v; }
__device__ __forceinline__ void sts32(uint32_t a, uint32_t v) { asm volatile("st.shared.b32 [%0], %1;" :: "r"(a), "r"(v) : "memory"); }
__device__ __forceinline__ void sts16(uint32_t a, uint32_t v) { asm volatile("{\n.reg .b16 h;\ncvt.u16.u32 h, %1;\nst.shared.b16 [%0], h;\n}" :: "r"(a), "r"(v) : "memory"); }
__device__ __forceinline__ void sts64(uint32_t a, uint32_t v, uint32_t w) { asm volatile("st.shared.v2.b32 [%0], {%1, %2};" :: "r"(a), "r"(v), "r"(w) : "memory"); }
__device__ __forceinline__ void fence_gpu() { asm volatile("fence.acq_rel.gpu;" ::: "memory"); }
__device__ __forceinline__ void fence_async() { asm volatile("fence.proxy.async.shared::cta;" ::: "memory"); }
__device__ __forceinline__ void red_add(uint32_t* p) { asm volatile("red.relaxed.gpu.global.add.u32 [%0], 1;" :: "l"(p) : "memory"); }
__device__ __forceinline__ void wg_fence() { asm volatile("wgmma.fence.sync.aligned;" ::: "memory"); }
__device__ __forceinline__ void wg_commit() { asm volatile("wgmma.commit_group.sync.aligned;" ::: "memory"); }
template<int N> __device__ __forceinline__ void wg_wait() { asm volatile("wgmma.wait_group.sync.aligned %0;" :: "n"(N) : "memory"); }
constexpr uint32_t SB0 = 1024;
__host__ __device__ constexpr uint32_t desc_lo(uint32_t off, uint32_t lbo) { return ((SB0 + off) >> 4) | ((lbo >> 4) << 16); }
__host__ __device__ constexpr uint32_t desc_hi(uint32_t sbo, uint32_t mode) { return (sbo >> 4) | (mode << 30); }
__device__ __forceinline__ void bar_sync(int id, int n) { asm volatile("bar.sync %0, %1;" :: "r"(id), "r"(n) : "memory"); }
__device__ __forceinline__ void bar_arrive(int id, int n) { asm volatile("bar.arrive %0, %1;" :: "r"(id), "r"(n) : "memory"); }
__device__ __forceinline__ void ld_rlx128(uint32_t* v, const void* p) {
  asm volatile("ld.relaxed.gpu.global.v4.b32 {%0, %1, %2, %3}, [%4];" : "=r"(v[0]), "=r"(v[1]), "=r"(v[2]), "=r"(v[3]) : "l"(p) : "memory");
}
__device__ __forceinline__ void st_rlx128(void* p, uint32_t a, uint32_t b, uint32_t c, uint32_t d) {
  asm volatile("st.relaxed.gpu.global.v4.b32 [%0], {%1, %2, %3, %4};" :: "l"(p), "r"(a), "r"(b), "r"(c), "r"(d) : "memory");
}
__device__ __forceinline__ void ld_rlx64(uint32_t* v, const void* p) {
  asm volatile("ld.relaxed.gpu.global.v2.b32 {%0, %1}, [%2];" : "=r"(v[0]), "=r"(v[1]) : "l"(p) : "memory");
}
__device__ __forceinline__ void st_rlx64(void* p, uint32_t a, uint32_t b) {
  asm volatile("st.relaxed.gpu.global.v2.b32 [%0], {%1, %2};" :: "l"(p), "r"(a), "r"(b) : "memory");
}
__device__ __forceinline__ uint32_t set_tag(uint32_t w, uint32_t tag) { return (w & ~1u) | tag; }
__device__ __forceinline__ void st_rlx32(void* p, uint32_t a) { asm volatile("st.relaxed.gpu.global.b32 [%0], %1;" :: "l"(p), "r"(a) : "memory"); }
__device__ __forceinline__ uint32_t ld_rlx32(const void* p) { uint32_t v; asm volatile("ld.relaxed.gpu.global.b32 %0, [%1];" : "=r"(v) : "l"(p) : "memory"); return v; }
__device__ __forceinline__ uint32_t lane_id() { uint32_t v; asm volatile("mov.u32 %0, %laneid;" : "=r"(v)); return v; }
__device__ __forceinline__ uint32_t gtime32() { uint32_t v; asm volatile("mov.u32 %0, %globaltimer_lo;" : "=r"(v) :: "memory"); return v; }
__device__ __forceinline__ void post_hint(uint32_t* hint, uint32_t saddr, uint32_t zero) {
  asm volatile("{\n.reg .pred p;\n.reg .b32 z;\n.reg .b64 t;\nmov.u64 t, 0;\nld.volatile.shared.b32 z, [%1];\nand.b32 z, z, %2;\nsetp.eq.u32 p, z, 0;\n@p mov.u64 t, %globaltimer;\n"
               "red.relaxed.gpu.global.max.u64 [%0 + 8], t;\nred.relaxed.gpu.global.add.u32 [%0], 1;\n}" :: "l"(hint), "r"(saddr), "r"(zero) : "memory");
}
__device__ __forceinline__ uint32_t launch_no(uint32_t v) { asm volatile("shr.u32 %0, %0, 7;" : "+r"(v)); return v + 1; }
__device__ __forceinline__ int warp_id() {
  int v; asm volatile("{\n.reg .b32 t;\nmov.u32 t, %tid.x;\nshr.u32 t, t, 5;\nredux.sync.max.u32 %0, t, -1;\n}" : "=r"(v)); return v;
}
__device__ __forceinline__ uint32_t clock32() { uint32_t c; asm volatile("mov.u32 %0, %clock;" : "=r"(c) :: "memory"); return c; }
__device__ __forceinline__ uint32_t pack2(float lo, float hi) { uint32_t r; asm("cvt.rn.bf16x2.f32 %0, %1, %2;" : "=r"(r) : "f"(hi), "f"(lo)); return r; }
__device__ __forceinline__ float bf_lo(uint32_t w) { return __uint_as_float(w << 16); }
__device__ __forceinline__ float bf_hi(uint32_t w) { return __uint_as_float(w & 0xFFFF0000u); }
__device__ __forceinline__ uint32_t hadd2(uint32_t a, uint32_t b) { uint32_t r; asm("add.rn.bf16x2 %0, %1, %2;" : "=r"(r) : "r"(a), "r"(b)); return r; }
__device__ __forceinline__ uint32_t hmul2(uint32_t a, uint32_t b) { uint32_t r; asm("mul.rn.bf16x2 %0, %1, %2;" : "=r"(r) : "r"(a), "r"(b)); return r; }
__device__ __forceinline__ uint32_t hfma2(uint32_t a, uint32_t b, uint32_t c) { uint32_t r; asm("fma.rn.bf16x2 %0, %1, %2, %3;" : "=r"(r) : "r"(a), "r"(b), "r"(c)); return r; }
__device__ __forceinline__ uint32_t ne2(uint32_t a, uint32_t b, uint32_t t) {
  uint32_t u; asm("lop3.b32 %0, %1, %2, %3, 0x7E;" : "=r"(u) : "r"(a), "r"(b), "r"(t)); return u;
}
__device__ __forceinline__ uint32_t or3(uint32_t a, uint32_t b, uint32_t c) {
  uint32_t u; asm("lop3.b32 %0, %1, %2, %3, 0xFE;" : "=r"(u) : "r"(a), "r"(b), "r"(c)); return u;
}
__device__ __forceinline__ float silu_h(float h) {
  float t; asm("tanh.approx.f32 %0, %1;" : "=f"(t) : "f"(h));
  return fmaf(h, t, h);
}
template<typename T> __device__ __forceinline__ T* opaque(T* p) { asm volatile("" : "+l"(p)); return p; }
__device__ __forceinline__ uint32_t opaque(uint32_t v) { asm volatile("" : "+r"(v)); return v; }
#define PIN(n) do { if (never == 1 + (n)) __trap(); } while (0)

__device__ __forceinline__ void wgmma_rs_n192_t1a(float* d, uint32_t a0, uint32_t a1, uint32_t a2, uint32_t a3, uint32_t dlo, uint32_t dhi) {
  asm volatile("{\n.reg .pred p;\n.reg .b64 db;\nsetp.ne.b32 p, 1, 0;\nmov.b64 db, {%100, %101};\n"
    "wgmma.mma_async.sync.aligned.m64n192k16.f32.bf16.bf16 {"
    "%0,%1,%2,%3,%4,%5,%6,%7,%8,%9,%10,%11,%12,%13,%14,%15,"
    "%16,%17,%18,%19,%20,%21,%22,%23,%24,%25,%26,%27,%28,%29,%30,%31,"
    "%32,%33,%34,%35,%36,%37,%38,%39,%40,%41,%42,%43,%44,%45,%46,%47,"
    "%48,%49,%50,%51,%52,%53,%54,%55,%56,%57,%58,%59,%60,%61,%62,%63,"
    "%64,%65,%66,%67,%68,%69,%70,%71,%72,%73,%74,%75,%76,%77,%78,%79,"
    "%80,%81,%82,%83,%84,%85,%86,%87,%88,%89,%90,%91,%92,%93,%94,%95"
    "}, {%96,%97,%98,%99}, db, p, 1, 1, 1;\n}"
    : "+f"(d[0]), "+f"(d[1]), "+f"(d[2]), "+f"(d[3]), "+f"(d[4]), "+f"(d[5]), "+f"(d[6]), "+f"(d[7]),
      "+f"(d[8]), "+f"(d[9]), "+f"(d[10]), "+f"(d[11]), "+f"(d[12]), "+f"(d[13]), "+f"(d[14]), "+f"(d[15]),
      "+f"(d[16]), "+f"(d[17]), "+f"(d[18]), "+f"(d[19]), "+f"(d[20]), "+f"(d[21]), "+f"(d[22]), "+f"(d[23]),
      "+f"(d[24]), "+f"(d[25]), "+f"(d[26]), "+f"(d[27]), "+f"(d[28]), "+f"(d[29]), "+f"(d[30]), "+f"(d[31]),
      "+f"(d[32]), "+f"(d[33]), "+f"(d[34]), "+f"(d[35]), "+f"(d[36]), "+f"(d[37]), "+f"(d[38]), "+f"(d[39]),
      "+f"(d[40]), "+f"(d[41]), "+f"(d[42]), "+f"(d[43]), "+f"(d[44]), "+f"(d[45]), "+f"(d[46]), "+f"(d[47]),
      "+f"(d[48]), "+f"(d[49]), "+f"(d[50]), "+f"(d[51]), "+f"(d[52]), "+f"(d[53]), "+f"(d[54]), "+f"(d[55]),
      "+f"(d[56]), "+f"(d[57]), "+f"(d[58]), "+f"(d[59]), "+f"(d[60]), "+f"(d[61]), "+f"(d[62]), "+f"(d[63]),
      "+f"(d[64]), "+f"(d[65]), "+f"(d[66]), "+f"(d[67]), "+f"(d[68]), "+f"(d[69]), "+f"(d[70]), "+f"(d[71]),
      "+f"(d[72]), "+f"(d[73]), "+f"(d[74]), "+f"(d[75]), "+f"(d[76]), "+f"(d[77]), "+f"(d[78]), "+f"(d[79]),
      "+f"(d[80]), "+f"(d[81]), "+f"(d[82]), "+f"(d[83]), "+f"(d[84]), "+f"(d[85]), "+f"(d[86]), "+f"(d[87]),
      "+f"(d[88]), "+f"(d[89]), "+f"(d[90]), "+f"(d[91]), "+f"(d[92]), "+f"(d[93]), "+f"(d[94]), "+f"(d[95])
    : "r"(a0), "r"(a1), "r"(a2), "r"(a3), "r"(dlo), "r"(dhi));
}
__device__ __forceinline__ void wgmma_rs_n192_t1z(float* d, uint32_t a0, uint32_t a1, uint32_t a2, uint32_t a3, uint32_t dlo, uint32_t dhi) {
  asm volatile("{\n.reg .pred p;\n.reg .b64 db;\nsetp.ne.b32 p, 0, 0;\nmov.b64 db, {%100, %101};\n"
    "wgmma.mma_async.sync.aligned.m64n192k16.f32.bf16.bf16 {"
    "%0,%1,%2,%3,%4,%5,%6,%7,%8,%9,%10,%11,%12,%13,%14,%15,"
    "%16,%17,%18,%19,%20,%21,%22,%23,%24,%25,%26,%27,%28,%29,%30,%31,"
    "%32,%33,%34,%35,%36,%37,%38,%39,%40,%41,%42,%43,%44,%45,%46,%47,"
    "%48,%49,%50,%51,%52,%53,%54,%55,%56,%57,%58,%59,%60,%61,%62,%63,"
    "%64,%65,%66,%67,%68,%69,%70,%71,%72,%73,%74,%75,%76,%77,%78,%79,"
    "%80,%81,%82,%83,%84,%85,%86,%87,%88,%89,%90,%91,%92,%93,%94,%95"
    "}, {%96,%97,%98,%99}, db, p, 1, 1, 1;\n}"
    : "+f"(d[0]), "+f"(d[1]), "+f"(d[2]), "+f"(d[3]), "+f"(d[4]), "+f"(d[5]), "+f"(d[6]), "+f"(d[7]),
      "+f"(d[8]), "+f"(d[9]), "+f"(d[10]), "+f"(d[11]), "+f"(d[12]), "+f"(d[13]), "+f"(d[14]), "+f"(d[15]),
      "+f"(d[16]), "+f"(d[17]), "+f"(d[18]), "+f"(d[19]), "+f"(d[20]), "+f"(d[21]), "+f"(d[22]), "+f"(d[23]),
      "+f"(d[24]), "+f"(d[25]), "+f"(d[26]), "+f"(d[27]), "+f"(d[28]), "+f"(d[29]), "+f"(d[30]), "+f"(d[31]),
      "+f"(d[32]), "+f"(d[33]), "+f"(d[34]), "+f"(d[35]), "+f"(d[36]), "+f"(d[37]), "+f"(d[38]), "+f"(d[39]),
      "+f"(d[40]), "+f"(d[41]), "+f"(d[42]), "+f"(d[43]), "+f"(d[44]), "+f"(d[45]), "+f"(d[46]), "+f"(d[47]),
      "+f"(d[48]), "+f"(d[49]), "+f"(d[50]), "+f"(d[51]), "+f"(d[52]), "+f"(d[53]), "+f"(d[54]), "+f"(d[55]),
      "+f"(d[56]), "+f"(d[57]), "+f"(d[58]), "+f"(d[59]), "+f"(d[60]), "+f"(d[61]), "+f"(d[62]), "+f"(d[63]),
      "+f"(d[64]), "+f"(d[65]), "+f"(d[66]), "+f"(d[67]), "+f"(d[68]), "+f"(d[69]), "+f"(d[70]), "+f"(d[71]),
      "+f"(d[72]), "+f"(d[73]), "+f"(d[74]), "+f"(d[75]), "+f"(d[76]), "+f"(d[77]), "+f"(d[78]), "+f"(d[79]),
      "+f"(d[80]), "+f"(d[81]), "+f"(d[82]), "+f"(d[83]), "+f"(d[84]), "+f"(d[85]), "+f"(d[86]), "+f"(d[87]),
      "+f"(d[88]), "+f"(d[89]), "+f"(d[90]), "+f"(d[91]), "+f"(d[92]), "+f"(d[93]), "+f"(d[94]), "+f"(d[95])
    : "r"(a0), "r"(a1), "r"(a2), "r"(a3), "r"(dlo), "r"(dhi));
}
__device__ __forceinline__ void wgmma_n192_t1(float* d, const uint32_t* a, uint32_t dlo, uint32_t dhi, bool acc) {
  if (acc) wgmma_rs_n192_t1a(d, a[0], a[1], a[2], a[3], dlo, dhi); else wgmma_rs_n192_t1z(d, a[0], a[1], a[2], a[3], dlo, dhi);
}
__device__ __forceinline__ void wgmma_rs_n32_t1a(float* d, uint32_t a0, uint32_t a1, uint32_t a2, uint32_t a3, uint32_t dlo, uint32_t dhi) {
  asm volatile("{\n.reg .pred p;\n.reg .b64 db;\nsetp.ne.b32 p, 1, 0;\nmov.b64 db, {%20, %21};\n"
    "wgmma.mma_async.sync.aligned.m64n32k16.f32.bf16.bf16 {"
    "%0,%1,%2,%3,%4,%5,%6,%7,%8,%9,%10,%11,%12,%13,%14,%15"
    "}, {%16,%17,%18,%19}, db, p, 1, 1, 1;\n}"
    : "+f"(d[0]), "+f"(d[1]), "+f"(d[2]), "+f"(d[3]), "+f"(d[4]), "+f"(d[5]), "+f"(d[6]), "+f"(d[7]),
      "+f"(d[8]), "+f"(d[9]), "+f"(d[10]), "+f"(d[11]), "+f"(d[12]), "+f"(d[13]), "+f"(d[14]), "+f"(d[15])
    : "r"(a0), "r"(a1), "r"(a2), "r"(a3), "r"(dlo), "r"(dhi));
}
__device__ __forceinline__ void wgmma_rs_n32_t1z(float* d, uint32_t a0, uint32_t a1, uint32_t a2, uint32_t a3, uint32_t dlo, uint32_t dhi) {
  asm volatile("{\n.reg .pred p;\n.reg .b64 db;\nsetp.ne.b32 p, 0, 0;\nmov.b64 db, {%20, %21};\n"
    "wgmma.mma_async.sync.aligned.m64n32k16.f32.bf16.bf16 {"
    "%0,%1,%2,%3,%4,%5,%6,%7,%8,%9,%10,%11,%12,%13,%14,%15"
    "}, {%16,%17,%18,%19}, db, p, 1, 1, 1;\n}"
    : "+f"(d[0]), "+f"(d[1]), "+f"(d[2]), "+f"(d[3]), "+f"(d[4]), "+f"(d[5]), "+f"(d[6]), "+f"(d[7]),
      "+f"(d[8]), "+f"(d[9]), "+f"(d[10]), "+f"(d[11]), "+f"(d[12]), "+f"(d[13]), "+f"(d[14]), "+f"(d[15])
    : "r"(a0), "r"(a1), "r"(a2), "r"(a3), "r"(dlo), "r"(dhi));
}
__device__ __forceinline__ void wgmma_n32_t1(float* d, const uint32_t* a, uint32_t dlo, uint32_t dhi, bool acc) {
  if (acc) wgmma_rs_n32_t1a(d, a[0], a[1], a[2], a[3], dlo, dhi); else wgmma_rs_n32_t1z(d, a[0], a[1], a[2], a[3], dlo, dhi);
}
__device__ __forceinline__ void wgmma_rs_n64_t1a(float* d, uint32_t a0, uint32_t a1, uint32_t a2, uint32_t a3, uint32_t dlo, uint32_t dhi) {
  asm volatile("{\n.reg .pred p;\n.reg .b64 db;\nsetp.ne.b32 p, 1, 0;\nmov.b64 db, {%36, %37};\n"
    "wgmma.mma_async.sync.aligned.m64n64k16.f32.bf16.bf16 {"
    "%0,%1,%2,%3,%4,%5,%6,%7,%8,%9,%10,%11,%12,%13,%14,%15,"
    "%16,%17,%18,%19,%20,%21,%22,%23,%24,%25,%26,%27,%28,%29,%30,%31"
    "}, {%32,%33,%34,%35}, db, p, 1, 1, 1;\n}"
    : "+f"(d[0]), "+f"(d[1]), "+f"(d[2]), "+f"(d[3]), "+f"(d[4]), "+f"(d[5]), "+f"(d[6]), "+f"(d[7]),
      "+f"(d[8]), "+f"(d[9]), "+f"(d[10]), "+f"(d[11]), "+f"(d[12]), "+f"(d[13]), "+f"(d[14]), "+f"(d[15]),
      "+f"(d[16]), "+f"(d[17]), "+f"(d[18]), "+f"(d[19]), "+f"(d[20]), "+f"(d[21]), "+f"(d[22]), "+f"(d[23]),
      "+f"(d[24]), "+f"(d[25]), "+f"(d[26]), "+f"(d[27]), "+f"(d[28]), "+f"(d[29]), "+f"(d[30]), "+f"(d[31])
    : "r"(a0), "r"(a1), "r"(a2), "r"(a3), "r"(dlo), "r"(dhi));
}
__device__ __forceinline__ void wgmma_rs_n64_t1z(float* d, uint32_t a0, uint32_t a1, uint32_t a2, uint32_t a3, uint32_t dlo, uint32_t dhi) {
  asm volatile("{\n.reg .pred p;\n.reg .b64 db;\nsetp.ne.b32 p, 0, 0;\nmov.b64 db, {%36, %37};\n"
    "wgmma.mma_async.sync.aligned.m64n64k16.f32.bf16.bf16 {"
    "%0,%1,%2,%3,%4,%5,%6,%7,%8,%9,%10,%11,%12,%13,%14,%15,"
    "%16,%17,%18,%19,%20,%21,%22,%23,%24,%25,%26,%27,%28,%29,%30,%31"
    "}, {%32,%33,%34,%35}, db, p, 1, 1, 1;\n}"
    : "+f"(d[0]), "+f"(d[1]), "+f"(d[2]), "+f"(d[3]), "+f"(d[4]), "+f"(d[5]), "+f"(d[6]), "+f"(d[7]),
      "+f"(d[8]), "+f"(d[9]), "+f"(d[10]), "+f"(d[11]), "+f"(d[12]), "+f"(d[13]), "+f"(d[14]), "+f"(d[15]),
      "+f"(d[16]), "+f"(d[17]), "+f"(d[18]), "+f"(d[19]), "+f"(d[20]), "+f"(d[21]), "+f"(d[22]), "+f"(d[23]),
      "+f"(d[24]), "+f"(d[25]), "+f"(d[26]), "+f"(d[27]), "+f"(d[28]), "+f"(d[29]), "+f"(d[30]), "+f"(d[31])
    : "r"(a0), "r"(a1), "r"(a2), "r"(a3), "r"(dlo), "r"(dhi));
}
__device__ __forceinline__ void wgmma_n64_t1(float* d, const uint32_t* a, uint32_t dlo, uint32_t dhi, bool acc) {
  if (acc) wgmma_rs_n64_t1a(d, a[0], a[1], a[2], a[3], dlo, dhi); else wgmma_rs_n64_t1z(d, a[0], a[1], a[2], a[3], dlo, dhi);
}
__device__ __forceinline__ void wgmma_rs_n32_t0a(float* d, uint32_t a0, uint32_t a1, uint32_t a2, uint32_t a3, uint32_t dlo, uint32_t dhi) {
  asm volatile("{\n.reg .pred p;\n.reg .b64 db;\nsetp.ne.b32 p, 1, 0;\nmov.b64 db, {%20, %21};\n"
    "wgmma.mma_async.sync.aligned.m64n32k16.f32.bf16.bf16 {"
    "%0,%1,%2,%3,%4,%5,%6,%7,%8,%9,%10,%11,%12,%13,%14,%15"
    "}, {%16,%17,%18,%19}, db, p, 1, 1, 0;\n}"
    : "+f"(d[0]), "+f"(d[1]), "+f"(d[2]), "+f"(d[3]), "+f"(d[4]), "+f"(d[5]), "+f"(d[6]), "+f"(d[7]),
      "+f"(d[8]), "+f"(d[9]), "+f"(d[10]), "+f"(d[11]), "+f"(d[12]), "+f"(d[13]), "+f"(d[14]), "+f"(d[15])
    : "r"(a0), "r"(a1), "r"(a2), "r"(a3), "r"(dlo), "r"(dhi));
}
__device__ __forceinline__ void wgmma_rs_n32_t0z(float* d, uint32_t a0, uint32_t a1, uint32_t a2, uint32_t a3, uint32_t dlo, uint32_t dhi) {
  asm volatile("{\n.reg .pred p;\n.reg .b64 db;\nsetp.ne.b32 p, 0, 0;\nmov.b64 db, {%20, %21};\n"
    "wgmma.mma_async.sync.aligned.m64n32k16.f32.bf16.bf16 {"
    "%0,%1,%2,%3,%4,%5,%6,%7,%8,%9,%10,%11,%12,%13,%14,%15"
    "}, {%16,%17,%18,%19}, db, p, 1, 1, 0;\n}"
    : "+f"(d[0]), "+f"(d[1]), "+f"(d[2]), "+f"(d[3]), "+f"(d[4]), "+f"(d[5]), "+f"(d[6]), "+f"(d[7]),
      "+f"(d[8]), "+f"(d[9]), "+f"(d[10]), "+f"(d[11]), "+f"(d[12]), "+f"(d[13]), "+f"(d[14]), "+f"(d[15])
    : "r"(a0), "r"(a1), "r"(a2), "r"(a3), "r"(dlo), "r"(dhi));
}
__device__ __forceinline__ void wgmma_n32_t0(float* d, const uint32_t* a, uint32_t dlo, uint32_t dhi, bool acc) {
  if (acc) wgmma_rs_n32_t0a(d, a[0], a[1], a[2], a[3], dlo, dhi); else wgmma_rs_n32_t0z(d, a[0], a[1], a[2], a[3], dlo, dhi);
}

__device__ __forceinline__ void wait_clock(uint32_t t) {
  uint32_t left;
  while ((left = t - clock32()) < 32768u) { if (left > 384u) __nanosleep(SLEEPNS); }
}
__device__ __forceinline__ uint32_t poll_hint(const uint32_t* hint, uint32_t target) {
  uint32_t it = 0, v[4];
  while (ld_rlx128(v, hint), __any_sync(~0u, (int)((v[0] - target) << 3) < 0)) { if (++it > SPIN_LIMIT) SPIN_FAIL(__LINE__) }
  const int rel_ns = v[2] - gtime32();
  return clock32() + ((rel_ns * 7) >> 2);
}

__host__ __device__ constexpr int kchunk(int c) { return c == 0 ? 3 : c <= 3 ? c - 1 : c; }
template<int KIND> __device__ __forceinline__ void conv_step(float* ac, const uint32_t* af, uint32_t hd, int c, int j) {
  const int col0 = KIND == 1 ? 128 - 16 * j : -16 * j;
  #pragma unroll
  for (int b = 0; b < 4; b++)
    if (KIND == 1 || b >= (j >> 1))
      wgmma_n32_t0(ac + 16 * b, af + 4 * j, hd + desc_lo(CV_H + c * H_PITCH + H_PAD - 16 + (col0 + 32 * b) * 16, 16), desc_hi(128, 0), KIND == 2 || j != 0);
}
struct Maps { uint8_t role[64]; CUtensorMap w1a, w1b, w2a, w2b, w2c, w2d, q;
};

struct Rows {
  uint32_t xw[14], yw[14], nmp[2], s1[2], s2[2], rr[2], nn[2];
  __device__ __forceinline__ void accum(int w, bool first) {
    const uint32_t d = hadd2(xw[w], nmp[w & 1]);
    s1[w & 1] = first ? d : hadd2(s1[w & 1], d); s2[w & 1] = hfma2(d, d, first ? 0u : s2[w & 1]);
  }
  __device__ __forceinline__ void finish(uint32_t scr, int barid, int warp, int lane, float scale) {
    const bool b1 = lane & 2, b0 = lane & 1;
    const uint32_t k1 = b1 ? s1[1] : s1[0], k2 = b1 ? s2[1] : s2[0];
    const uint32_t o1 = __shfl_xor_sync(~0u, b1 ? s1[0] : s1[1], 2), o2 = __shfl_xor_sync(~0u, b1 ? s2[0] : s2[1], 2);
    const float f1 = (bf_lo(k1) + bf_hi(k1)) + (bf_lo(o1) + bf_hi(o1)), f2 = (bf_lo(k2) + bf_hi(k2)) + (bf_lo(o2) + bf_hi(o2));
    float v = (b0 ? f2 : f1) + __shfl_xor_sync(~0u, b0 ? f1 : f2, 1);
    v += __shfl_xor_sync(~0u, v, 16);
    asm volatile("st.shared.f32 [%0], %1;" :: "r"(scr + warp * 4), "f"(v) : "memory");
    bar_sync(barid, 128);
    uint32_t u[4]; lds128(u, scr);
    v = ((__uint_as_float(u[0]) + __uint_as_float(u[1])) + (__uint_as_float(u[2]) + __uint_as_float(u[3]))) * (1.0f / D_);
    #pragma unroll
    for (int h2 = 0; h2 < 2; h2++) {
      const float m = __shfl_sync(~0u, v, 2 * h2, 4), e2 = __shfl_sync(~0u, v, 2 * h2 + 1, 4);
      float rs; asm("rsqrt.approx.ftz.f32 %0, %1;" : "=f"(rs) : "f"(fmaxf(fmaf(-m, m, e2), 0.f) + 1e-5f));
      rs *= scale;
      const float nm = bf_lo(nmp[h2]) - m;
      nmp[h2] = pack2(nm, nm); rr[h2] = pack2(rs, rs); nn[h2] = pack2(nm * rs, nm * rs);
    }
  }
  __device__ __forceinline__ void load_y(const uint8_t* gs, int n8, int warp) {
    const int ln = lane_id();
    const uint8_t* yp = g_S + n8 * REC + R_YT + ((ln >> 2) & 3) * 8 + (ln & 3) * 32;
    const uint8_t* ya = yp + (warp >> 1) * 4096 + (warp & 1) * 512 + (ln >> 4) * 256;
    #pragma unroll
    for (int j = 0; j < 6; j++) ld_rlx64(&yw[2 * j], ya + (j >> 1) * 1024 + (j & 1) * 128);
    ld_rlx64(&yw[12], yp + 3072 + warp * 256 + (ln >> 4) * 128);
  }
  static __device__ __forceinline__ void load14(uint32_t* w, const uint8_t* pA, const uint8_t* pM) {
    #pragma unroll
    for (int j = 0; j < 3; j++) ld_rlx128(&w[4 * j], pA + j * 1024);
    ld_rlx64(&w[12], pM);
  }
  static __device__ __forceinline__ void store14(const uint32_t* w, uint8_t* pA, uint8_t* pM) {
    #pragma unroll
    for (int j = 0; j < 3; j++) st_rlx128(pA + j * 1024, w[4*j], w[4*j+1], w[4*j+2], w[4*j+3]);
    st_rlx64(pM, w[12], w[13]);
  }
  __device__ __forceinline__ void gate_emit(uint32_t scr, int barid, int warp, int lane, uint8_t* pA, uint8_t* pM, uint32_t tag) {
    #pragma unroll
    for (int w = 0; w < 14; w++) { xw[w] = hfma2(hfma2(xw[w], rr[w & 1], nn[w & 1]), yw[w], xw[w]); accum(w, w < 2); }
    finish(scr + 256, barid, warp, lane, 0.5f);
    uint32_t xn[14];
    #pragma unroll
    for (int w = 0; w < 14; w++) { xn[w] = hfma2(xw[w], rr[w & 1], nn[w & 1]); if ((w & 3) == 0) xn[w] = set_tag(xn[w], tag); }
    st_rlx64(pM + R_XN, xn[12], xn[13]);
    #pragma unroll
    for (int j = 0; j < 3; j++) st_rlx128(pA + R_XN + j * 1024, xn[4*j], xn[4*j+1], xn[4*j+2], xn[4*j+3]);
  }
};

#define WARP const int wid = warp_id(), wg = wid >> 2, warp = wid & 3; (void)wg;
#define ROLE const int rl_ = mp.role[opaque(blockIdx.x) >> 1], r = rl_ & 15, pc = rl_ >> 4, f = pc * 2 + rank;
#define OWNER_MAP \
  const int lane = lane_id(), kl = lane >> 4, gl = (lane >> 2) & 3; \
  const int offA = (warp >> 1) * 4096 + (warp & 1) * 512 + lane * 16, offM = 3072 + warp * 256 + (lane & 15) * 16 + kl * 8; \
  const uint32_t scr = sb + SM_RED + (wg & 1) * 512 + (lane & 15) * 16;

__global__ void __cluster_dims__(2, 1, 1) __launch_bounds__(384, 1)
k_main(const uint8_t* __restrict__ kin, const uint8_t* __restrict__ vin, uint8_t* gs, const uint2* __restrict__ shk,
       const uint8_t* __restrict__ hin, int never, const __nv_bfloat16* __restrict__ q, const __nv_bfloat16* __restrict__ dvec,
       const uint8_t* __restrict__ w1, const uint8_t* __restrict__ w2, __nv_bfloat16* __restrict__ out, const __grid_constant__ Maps mp) {
  extern __shared__ __align__(1024) uint8_t sm[];
  const uint32_t sb = SB0 + ((blockIdx.x & 1) << 24);
  const uint32_t bar_full = sb + SM_BAR, bar_empty = bar_full + 56, bar_xr = bar_empty + 56, bar_hf = bar_xr + 16, bar_he = bar_hf + 192, bar_go = bar_he + 32,
                 bar_hk = bar_go + 80, bar_cd = bar_hk + 8;
  const int tid = threadIdx.x;
  const int wg0 = warp_id() >> 2;
  const int rank = blockIdx.x & 1;
  const int cb = blockIdx.x;
  const bool conv = cb < 112;
  auto load_tile = [&](int st, int i0, int i1) {
    const int c16 = tid & 7, r0 = tid >> 3, row0 = st * 1024 + (cb & 15) * 64;
    const size_t go = (size_t)(row0 + r0) * 896 + (cb >> 4) * 128 + c16 * 16;
    const uint32_t so = sb + (st ? CV_T1 : CV_T0) + r0 * 128 + ((c16 ^ (r0 & 7)) << 4);
    #pragma unroll
    for (int i = i0; i < i1; i++) {
      cp_async16(so + 1024 + i * 4096, kin + go + i * 32 * 896, 16);
      cp_async16(so + 9216 + i * 4096, vin + go + i * 32 * 896, 16);
    }
    if (i1 == 2) {
      if (r0 >= 5 && r0 < 8) cp_async16(so, row0 ? kin + go - 8 * 896 : kin, row0 ? 16 : 0);
      asm volatile("cp.async.commit_group;" ::: "memory");
    }
  };

  if (wg0 < 2) {
    if (conv) load_tile(0, 0, 2);
    const uint32_t t0 = clock32();
    asm volatile("barrier.cluster.arrive.relaxed.aligned;" ::: "memory");
    asm volatile("setmaxnreg.inc.sync.aligned.u32 240;");
    WARP
    const int hf = wg;
    Rows R;
    {
      const int lane = lane_id(), g = lane >> 2, t4 = lane & 3, tl = warp * 32 + lane;
      STAMP(2, 24);
      uint32_t et = ld_rlx32(g_HY + (lane & never));
      float ac[2][64];
      uint32_t af[2][32], cw[2] = {0, 0};
      float chi[4] = {0.f, 0.f, 0.f, 0.f};
      const uint32_t pw0 = sb + CV_P + 64;
      const int n0 = g + 16 * warp - 2 * t4;
      const uint32_t a1 = pw0 + hf * 2 * PW_PITCH + (n0 + 8 * (n0 >> 5)) * 4, a0 = pw0 + hf * 2 * PW_PITCH + (n0 + 8 + 8 * ((n0 + 8) >> 5)) * 4;
      const uint32_t hd = hf * (2 * H_PITCH >> 4);
      auto lda = [&](int c, int late, int j0, int j1) {
        #pragma unroll
        for (int j = j0; j < j1; j++) {
          const uint32_t o = c * PW_PITCH + (late * 8 + j) * 640;
          af[c][4*j] = lds32(a0 + o); af[c][4*j+1] = lds32(a0 + o + 320); af[c][4*j+2] = lds32(a1 + o); af[c][4*j+3] = lds32(a1 + o + 320);
        }
      };
      auto cepi = [&](int part) {
        const uint32_t sw_ = sb + CV_S + hf * 4 * SCR_W;
        const uint32_t wa = sw_ + warp * SCR_W + (t4 + 3) * 64 + ((g ^ (((t4 + 3) & 2) << 1)) << 3);
        if (t4) sts64(wa - 256, cw[0], cw[1]);
        #pragma unroll
        for (int jn = 0; jn < 16; jn++) {
          const uint32_t w0 = pack2(ac[0][4*jn] + (jn ? ac[0][4*jn-2] : chi[0]), ac[1][4*jn] + (jn ? ac[1][4*jn-2] : chi[1]));
          const uint32_t w1 = pack2(ac[0][4*jn+1] + (jn ? ac[0][4*jn-1] : chi[2]), ac[1][4*jn+1] + (jn ? ac[1][4*jn-1] : chi[3]));
          sts64(wa + jn * 256, w0, w1);
          if (jn == 15) { cw[0] = w0; cw[1] = w1; }
        }
        if (part == 0) {
          #pragma unroll
          for (int i = 0; i < 4; i++) asm volatile("add.f32 %0, %1, 0f00000000;" : "=f"(chi[i]) : "f"(ac[i & 1][62 + (i >> 1)]));
        }
        bar_sync(3 + hf, 128);
        uint8_t* dst = g_S + (part * 128 + 2 * (tl >> 2)) * REC + R_YT + (cb * 2 + hf) * 32 + t4 * 8;
        #pragma unroll
        for (int h2 = 0; h2 < 2; h2++) {
          uint32_t u[4][4], y[4];
          #pragma unroll
          for (int w = 0; w < 4; w++) lds128(u[w], sw_ + w * SCR_W + ((tl >> 2) + 3 - w) * 64 + ((t4 ^ ((g + 3 - w) & 2)) << 4) + h2 * 2048);
          #pragma unroll
          for (int i = 0; i < 4; i++) y[i] = hadd2(hadd2(u[0][i], u[1][i]), hadd2(u[2][i], u[3][i]));
          st_rlx64(dst + h2 * 64 * REC, set_tag(y[0], et), y[2]);
          st_rlx64(dst + h2 * 64 * REC + REC, set_tag(y[1], et), y[3]);
        }
      };
      uint32_t WW[2][2][4];
      auto fetch = [&](uint32_t (&W)[2][4], int st, int cp) {
        const uint8_t* src = g_KV + (cb * 4 + cp * 2) * 4096 + st * 2048 + tl * 16;
        ld_rlx128(W[0], src); ld_rlx128(W[1], src + 4096);
      };
      auto build = [&](uint32_t (&W)[2][4], int st, int cp) {
        uint32_t it = 0;
        while (__any_sync(~0u, ne2(W[0][0], W[1][0], et) & 1)) { if (++it > SPIN_LIMIT) SPIN_FAIL(__LINE__) fetch(W, st, cp); }
        #pragma unroll
        for (int i = 0; i < 2; i++) {
          const uint32_t a = pw0 + (cp * 2 + i) * PW_PITCH + ((st * 32 + (tl >> 2)) * 40 + t4 * 2) * 4;
          #pragma unroll
          for (int m = 0; m < 4; m++) {
            const uint32_t p = __shfl_sync(~0u, t4 == 3 ? W[i][(m + 3) & 3] : W[i][m], (t4 == 0 && m > 0) ? lane + 3 : lane - 1);
            if (m || lane) sts64(a + m * 32, __byte_perm(W[i][m], p, 0x5432), W[i][m]);
          }
          if (lane == 0) { sts16(a, W[i][0] >> 16); sts32(a + 4, W[i][0]); }
          if (lane == 31) sts16(a + 136 + 2, W[i][3]);
        }
      };
      auto load_q = [&](int h) {
        const int mg = lane & 3, mk = (lane >> 2) & 1, mh = (lane >> 3) & 1;
        const int row = mg * 2 + mh;
        const uint32_t qr = sb + CV_Q + h * 8192 + row * 128;
        #pragma unroll
        for (int j = 0; j < 3; j++) ldsm4(&R.xw[4 * j], qr + (warp >> 1) * 4096 + j * 1024 + ((((warp & 1) * 4 + mk * 2 + (lane >> 4)) ^ row) << 4));
        ldsm2(&R.xw[12], qr + 3072 + (((warp * 2 + mk) ^ row) << 4));
      };
      if (!conv) {
        et = launch_no(et) & 1;
        bar_sync(7, 384);
        bar_arrive(13, 288);
      } else {
        const int ch = (cb >> 4) * 64 + wid * 8 + g;
        const uint2 sw = __ldg(shk + ch);
        wait_clock(t0 + S2DELAY);
        load_tile(1, 0, 2);
        PIN(602);
        et = launch_no(et) & 1;
        {
          const uint32_t w0 = __byte_perm(sw.x, 0, 0x1010), w1 = __byte_perm(sw.x, 0, 0x3232), w2_ = __byte_perm(sw.y, 0, 0x1010), w3 = __byte_perm(sw.y, 0, 0x3232);
          uint8_t* dst = g_KV + ch * 4096 + (cb & 15) * 128 + t4 * 16;
          const int rl = lane ^ 1;
          uint32_t ka[4];
          #pragma unroll
          for (int j = 0; j < 4; j++) ka[j] = sb + CV_T0 + (8 + rl - j) * 128 + ((wid ^ ((rl - j) & 7)) << 4);
          #pragma unroll 1
          for (int st = opaque(0u); st < 2; st++) {
            if (st == 0) asm volatile("cp.async.wait_group 1;" ::: "memory"); else asm volatile("cp.async.wait_group 0;" ::: "memory");
            bar_sync(6, 256);
            STAMP(2, 31 - 15 * st);
            if (st) {
              if ((wid | lane) == 0) post_hint(g_HK + (cb >> 4) * 32, sb + SM_RED, never);
              wait_clock(t0 + F0MIN);
              fetch(WW[0], 0, hf);
            }
            #pragma unroll
            for (int tb = 0; tb < 2; tb++) {
              uint32_t kk[4][4], vv[4], o[4];
              #pragma unroll
              for (int j = 0; j < 4; j++) ldsm4t(kk[j], ka[j] + st * (CV_T1 - CV_T0) + tb * 4096);
              ldsm4t(vv, ka[0] + st * (CV_T1 - CV_T0) + 8192 + tb * 4096);
              #pragma unroll
              for (int m = 0; m < 4; m++) o[m] = hmul2(hfma2(kk[0][m], w0, hfma2(kk[1][m], w1, hfma2(kk[2][m], w2_, hmul2(kk[3][m], w3)))), vv[m]);
              st_rlx128(dst + st * 2048 + tb * 64, set_tag(o[0], et), o[1], o[2], o[3]);
            }
          }
        }
        STAMP(2, 17);
        bar_sync(7, 384);
        STAMP(2, 18);
        if (tl < 32) sts32(pw0 + (hf * 2 + (tl >> 4)) * PW_PITCH - 64 + (tl & 15) * 4, 0);
        if (tl >= 32 && tl < 34) sts16(pw0 + (hf * 2 + tl - 32) * PW_PITCH + 2, 0);
        mbar_wait(bar_hk, 0);
        build(WW[0], 0, hf);
        STAMP(2, 21);
        bar_sync(3 + hf, 128);
        STAMP(2, 19);
        lda(0, 0, 0, 8); lda(1, 0, 0, LDA1);
        #pragma unroll
        for (int c = 0; c < 2; c++) {
          wg_fence();
          #pragma unroll
          for (int j = 0; j < 8; j++) conv_step<0>(ac[c], af[c], hd, c, j);
          wg_commit();
          if (c == 0) {
            PIN(606);
            lda(1, 0, LDA1, 8);
            mbar_wait(bar_hk + 16, 0);
            fetch(WW[1], 1, hf);
          }
        }
        PIN(608);
        build(WW[1], 1, hf);
        bar_arrive(13, 288);
        wg_wait<0>();
        STAMP(2, 28);
        cepi(0);
        STAMP(2, 20);
      }
      const uint32_t q0 = sb + CV_Q + (g & 3) * 288, qs = sb + CV_Q + 7168 + (g & 3) * 32;
      auto qstats = [&](int h) {
        mbar_wait(bar_xr + h * 8, 0);
        load_q(h);
        R.nmp[0] = __byte_perm(lds32(q0 + h * 8192), 0, 0x1010) ^ 0x80008000u;
        R.nmp[1] = __byte_perm(lds32(q0 + h * 8192 + 144), 0, 0x1010) ^ 0x80008000u;
        #pragma unroll
        for (int w = 0; w < 14; w++) R.accum(w, w < 2);
        R.finish(sb + SM_RED + 768 - h * 256 + (lane & 15) * 16, 4, warp, lane, 1.0f);
      };
      if (hf) {
        qstats(0);
        sts64(qs, R.nmp[0], R.nmp[1]); sts64(qs + 8, R.rr[0], R.rr[1]); sts64(qs + 16, R.nn[0], R.nn[1]);
        bar_arrive(12, 256);
      }
      STAMP(2, 27);
      if (conv) {
        wg_fence();
        #pragma unroll
        for (int j = 0; j < 8; j++) conv_step<1>(ac[0], af[0], hd, 0, j);
        wg_commit();
        #pragma unroll
        for (int j = 0; j < 8; j++) {
          if (j == 0 || j == 1 || j == 4 || j == 5) wg_fence();
          conv_step<1>(ac[1], af[1], hd, 1, j);
          if (j == 0) { wg_commit(); wg_wait<1>(); lda(0, 1, 0, 8); }
          if (j == 3) wg_commit();
          if (j == 4) { wg_commit(); wg_wait<1>(); lda(1, 1, 0, 4); }
        }
        wg_commit();
        STAMP(2, 30);
        #pragma unroll
        for (int j = 0; j < 8; j++) {
          if (j < 2) wg_fence();
          conv_step<2>(ac[0], af[0], hd, 0, j);
          if (j == 0) { wg_commit(); wg_wait<1>(); lda(1, 1, 4, 8); }
        }
        wg_commit();
        wg_wait<0>();
      }
      ROLE
      const int n8 = hf * 128 + r * 8 + f;
      if (!hf) {
        mbar_wait(bar_go + 64, 0);
        STAMP(2, 16 + 9);
        R.load_y(gs, n8, warp);
        bar_sync(12, 256);
        load_q(0);
        uint32_t u[4]; lds128(u, qs); R.nmp[0] = u[0]; R.nmp[1] = u[1]; R.rr[0] = u[2]; R.rr[1] = u[3]; R.nn[0] = lds32(qs + 16); R.nn[1] = lds32(qs + 20);
      }
      if (conv) {
        wg_fence();
        #pragma unroll
        for (int j = 0; j < 8; j++) conv_step<2>(ac[1], af[1], hd, 1, j);
        wg_commit();
        wg_wait<0>();
        STAMP(2, 22);
      }
      if (lane == 0) mbar_arrive(bar_cd + 16);
      #pragma unroll 1
      for (int step = opaque(0u); step < 2; step++) {
        if (step != hf) {
          if (conv) {
            #pragma unroll
            for (int i = 0; i < 64; i++) asm volatile("" : "+f"(ac[0][i]), "+f"(ac[1][i]));
            cepi(1);
          }
          STAMP(2, 23);
        } else {
          const int kl = lane >> 4;
          if (hf) {
            qstats(1);
            if (lane == 0) mbar_arrive(bar_cd);
            mbar_wait(bar_go + 72, 0);
            STAMP(2, 16 + 9);
            R.load_y(gs, n8, warp);
          }
          uint32_t it = 0;
          while (__any_sync(~0u, (or3(ne2(R.yw[0], R.yw[2], et), ne2(R.yw[4], R.yw[6], et), ne2(R.yw[8], R.yw[10], et)) | (R.yw[12] ^ et)) & 1)) {
            if (++it > SPIN_LIMIT) SPIN_FAIL(__LINE__)
            R.load_y(gs, n8, warp);
          }
          STAMP(2, 16 + 10);
          uint8_t* rec = g_S + n8 * REC;
          R.gate_emit(sb + SM_RED + hf * 512 + (lane & 15) * 16, 3 + hf, warp, lane, rec + (warp >> 1) * 4096 + (warp & 1) * 512 + lane * 16,
                      rec + 3072 + warp * 256 + (lane & 15) * 16 + kl * 8, 1);
          sts64(sb + SM_BAR + 464 + hf * 32 + (g & 3) * 8, R.nmp[0], R.nmp[1]);
          STAMP(2, 16 + 13);
        }
      }
      if (!hf) { __syncwarp(); if (lane == 0) mbar_arrive(bar_cd); }
    }
    asm volatile("barrier.cluster.wait.aligned;" ::: "memory");
    ROLE
    OWNER_MAP
    const bool l0 = lane == 0;
    const int n8own = hf * 128 + r * 8 + f;
    uint8_t* const pX = opaque(g_S + (hf * 128 + r * 8 + warp * 2 + kl) * REC + (lane & 15) * 16);
    uint8_t* const pA = opaque(g_S + n8own * REC + offA);
    uint8_t* const pM = opaque(g_S + n8own * REC + offM);
    const uint32_t hloc = opaque(sb + SM_H + warp * 7168 + lane * 16);
    const uint32_t peer = mapa(sb, rank ^ 1) - sb;
    #pragma unroll 1
    for (int layer = opaque(0u); layer < 2; layer++) {
      const uint32_t tag = layer ^ 1;
      float acc[112];
      uint32_t xa[18][4];
      auto xload = [&](int k0, int k1) {
        #pragma unroll
        for (int k = k0; k < k1; k++) ld_rlx128(xa[k % 18], pX + R_XN + kchunk(k >> 2) * 1024 + (k & 3) * 256);
      };
      auto xwait = [&](int k0, int k1) {
        uint32_t it = 0;
        while (true) {
          uint32_t o = k0 ? 0 : ne2(xa[0][2], xa[1][2], tag) | ne2(xa[2][2], xa[3][2], tag);
          #pragma unroll
          for (int k = k0; k < k1; k += 4) o = or3(o, ne2(xa[k % 18][0], xa[(k + 1) % 18][0], tag), k + 2 < k1 ? ne2(xa[(k + 2) % 18][0], xa[(k + 3) % 18][0], tag) : 0);
          if (!__any_sync(~0u, o & 1)) break;
          if (++it > SPIN_LIMIT) SPIN_FAIL(__LINE__)
          xload(k0, k1);
        }
      };
      STAMP(wg, layer * 16 + 0);
      mbar_wait(bar_go + (hf * 4 + layer * 2) * 8, 0);
      STAMP(wg, layer * 16 + 15);
      xload(0, 8); xwait(0, 8); xload(8, 18);
      STAMP(wg, layer * 16 + 1);
      if (hf == 0) mbar_wait(bar_full, 0);
      if (hf == 1 || layer > 0) bar_sync(1 + hf, 256);
      #pragma unroll
      for (int c = 0; c < 7; c++) {
        if (hf == 0 && c && !(c & 1)) mbar_wait(bar_full + c * 4, 0);
        if (c == 0) STAMP(wg, layer * 16 + 2);
        if (c == 2) { PIN(312); xwait(8, 18); STAMP(wg, layer * 16 + 14); xload(18, 22); }
        wg_fence();
        #pragma unroll
        for (int ks = 0; ks < 4; ks++) {
          const uint32_t* a = xa[(4 * c + ks) % 18];
          wgmma_n192_t1(acc, a, desc_lo(c * SLOT + ks * 2048, 8192), desc_hi(1024, 1), (c | ks) != 0);
          wgmma_n32_t1(acc + 96, a, desc_lo(c * SLOT + 24576 + ks * 1024, 2048), desc_hi(512, 2), (c | ks) != 0);
          if (ks == 1 && c > 0) {
            wg_commit();
            wg_wait<1>();
            if (l0) mbar_arrive(bar_empty + (c - 1) * 8);
            if (c == 2) xload(22, 26);
            if (c == 4) { PIN(310); xwait(18, 26); xload(26, 28); }
            if (c == 6) { PIN(311); xwait(26, 28); }
            wg_fence();
          }
        }
        wg_commit();
      }
      bar_arrive(2 - hf, 256);
      wg_wait<0>();
      if (l0) mbar_arrive(bar_empty + 48);
      STAMP(wg, layer * 16 + 3);
      uint32_t hA[56], hB[56];
      const uint32_t bh = bar_hf + wid * 24;
      if (l0) { mbar_expect_tx(bh, 3072); mbar_expect_tx(bh + 8, 2560); mbar_expect_tx(bh + 16, 1536); }
      #pragma unroll
      for (int ks = 0; ks < 14; ks++) {
        #pragma unroll
        for (int i = 0; i < 4; i++) hA[4 * ks + i] = pack2(silu_h(acc[8 * ks + 2 * i]), silu_h(acc[8 * ks + 2 * i + 1]));
        if (ks == 0) mbar_wait(bar_he + warp * 8, hf);
        st_async128(hloc + peer + ks * 512, hA[4*ks], hA[4*ks+1], hA[4*ks+2], hA[4*ks+3], bh + peer + (ks < 6 ? 0 : ks < 11 ? 8 : 16));
        if (ks == 9) {
          mbar_wait(bh, layer);
          #pragma unroll
          for (int j = 0; j < 6; j++) lds128(&hB[4 * j], hloc + j * 512);
        } else if (ks & 1) PIN(ks);
      }
      STAMP(wg, layer * 16 + 4);
      mbar_wait(bh + 8, layer);
      #pragma unroll
      for (int j = 6; j < 11; j++) lds128(&hB[4 * j], hloc + j * 512);
      mbar_wait(bh + 16, layer);
      #pragma unroll
      for (int j = 11; j < 14; j++) lds128(&hB[4 * j], hloc + j * 512);
      __syncwarp();
      if (l0 && !(hf & layer)) mbar_arrive_remote(bar_he + warp * 8 + peer);
      STAMP(wg, layer * 16 + 8);
      uint8_t* const pP = pX + (pc * 7168 + rank * 4096);
      uint8_t* const pQ = pX + (pc * 7168 + 3072 + rank * 512);
      if (hf == 0) mbar_wait(bar_full, 1);
      bar_sync(1 + hf, 256);
      float o2[2][32];
      auto epi = [&](const float* o, uint8_t* dst, bool two) {
        const uint32_t w2 = pack2(o[4], o[5]);
        st_rlx128(dst, set_tag(pack2(o[0], o[1]), tag), pack2(o[2], o[3]), two ? set_tag(w2, tag) : w2, pack2(o[6], o[7]));
      };
      uint32_t pw[3][16], pm[8];
      auto pload = [&](int j) {
        #pragma unroll
        for (int s = 0; s < 4; s++) ld_rlx128(&pw[j][4 * s], pA + j * 1024 + s * 7168);
      };
      auto pmload = [&]() {
        #pragma unroll
        for (int s = 0; s < 4; s++) ld_rlx64(&pm[2 * s], pM + s * 7168);
      };
      auto pbad = [&](int j, uint32_t o) { return or3(o, ne2(pw[j][0], pw[j][4], tag), ne2(pw[j][8], pw[j][12], tag)); };
      #pragma unroll
      for (int sl = 0; sl < 7; sl++) {
        const int i = (sl + 1) >> 1;
        if (sl == 0) STAMP(wg, layer * 16 + 5);
        wg_fence();
        #pragma unroll
        for (int kk = 0; kk < (sl ? 14 : 28); kk++) {
          const int ks = kk % 14;
          const bool own = sl ? (sl & 1) : kk < 14;
          const uint32_t* h = own ? &hA[4 * ks] : &hB[4 * ks];
          if (sl) wgmma_n64_t1(o2[i & 1], h, desc_lo(sl * SLOT + ks * 2048, 4096), desc_hi(1024, 1), !(sl & 1) || kk != 0);
          else wgmma_n32_t1(o2[0], h, desc_lo(kk * 1024, 2048), desc_hi(512, 2), kk != 0);
          if (sl > 0 && kk == 4) {
            wg_commit();
            wg_wait<1>();
            if (l0) mbar_arrive(bar_empty + (sl - 1) * 8);
            if (sl == 2 && l0) mbar_arrive(bar_full + 32 + hf * 8);
            wg_fence();
          }
          if (sl == 6 && kk == AK) { wg_commit(); PIN(320); pload(0); wg_fence(); }
          if (sl > 0 && ((sl & 1) ? (kk == 6 || kk == 9 || kk == 12) : kk == 1)) {
            const int e = (sl & 1) ? (kk - 6) / 3 : 3;
            if (i > 1 || e < 2) {
              wg_commit();
              PIN(100 + sl * 32 + kk * 2);
              if (i == 1) epi(&o2[0][8 * e], pQ + e * 256, true);
              else epi(&o2[(i - 1) & 1][8 * e], pP + (i - 2) * 1024 + e * 256, false);
              PIN(101 + sl * 32 + kk * 2);
              if (sl == 5 && e == 2) pmload();
              wg_fence();
            }
          }
        }
        wg_commit();
        if (hf == 0 && (sl & 1)) mbar_wait(bar_full + (sl + 1) * 4, 1);
      }
      if (hf == 0 || layer == 0) bar_arrive(2 - hf, 256);
      asm volatile("ld.shared.v2.b32 {%0, %1}, [%2];" : "=r"(R.nmp[0]), "=r"(R.nmp[1]) : "r"(sb + SM_BAR + 464 + hf * 32 + gl * 8) : "memory");
      wg_wait<0>();
      STAMP(wg, layer * 16 + 6);
      uint32_t fw[16];
      #pragma unroll
      for (int i = 0; i < 16; i++) { fw[i] = pack2(o2[1][2 * i], o2[1][2 * i + 1]); if ((i & 3) == 0) fw[i] = set_tag(fw[i], tag); }
      #pragma unroll
      for (int e = 0; e < 4; e++) st_rlx128(pP + 2 * 1024 + e * 256, fw[4*e], fw[4*e+1], fw[4*e+2], fw[4*e+3]);
      if (l0) mbar_arrive(bar_empty + 48);
      STAMP(wg, layer * 16 + 7);
      PIN(300);
      {
        uint32_t it = 0;
        while (__any_sync(~0u, pbad(0, ne2(pm[0], pm[2], tag) | ne2(pm[4], pm[6], tag)) & 1)) {
          if (++it > SPIN_LIMIT) SPIN_FAIL(__LINE__)
          pmload(); pload(0);
        }
      }
      STAMP(wg, layer * 16 + 9);
      pload(1);
      auto psum = [&](int j, int e) { return hadd2(R.xw[4*j+e], hadd2(hadd2(pw[j][e], pw[j][4 + e]), hadd2(pw[j][8 + e], pw[j][12 + e]))); };
      #pragma unroll
      for (int e = 0; e < 2; e++) R.xw[12 + e] = hadd2(R.xw[12 + e], hadd2(hadd2(pm[e], pm[2 + e]), hadd2(pm[4 + e], pm[6 + e])));
      #pragma unroll
      for (int e = 0; e < 4; e++) R.xw[e] = psum(0, e);
      R.accum(12, true); R.accum(13, true);
      #pragma unroll
      for (int w = 0; w < 4; w++) R.accum(w, false);
      asm volatile("" : "+r"(R.s1[0]), "+r"(R.s1[1]), "+r"(R.s2[0]), "+r"(R.s2[1]));
      const uint32_t ln = lane_id();
      uint32_t* op = (uint32_t*)(out + n8own * 8 * D_) + ((ln >> 2) & 3) * D_;
      uint32_t* opa = opaque(op + (warp >> 1) * 128 + (warp & 1) * 16 + (ln >> 4) * 8 + (ln & 1) * 4 + (ln & 2));
      auto store_out = [&](int j) {
        #pragma unroll
        for (int h2 = 0; h2 < 2; h2++) {
          const uint32_t lo = R.xw[4*j+h2], hi = R.xw[4*j+2+h2], o = __shfl_xor_sync(~0u, (ln & 1) ? lo : hi, 1);
          *(uint2*)(opa + h2 * (D_ / 2) + j * 32) = (ln & 1) ? make_uint2(o, hi) : make_uint2(lo, o);
        }
      };
      STAMP(wg, layer * 16 + 13);
      mbar_wait(bar_go + (hf * 4 + layer * 2 + 1) * 8, 0);
      STAMP(wg, layer * 16 + 12);
      {
        uint32_t it = 0;
        Rows T;
        while (true) {
          pload(2);
          T.nmp[0] = R.nmp[0]; T.nmp[1] = R.nmp[1]; T.s1[0] = R.s1[0]; T.s1[1] = R.s1[1]; T.s2[0] = R.s2[0]; T.s2[1] = R.s2[1];
          #pragma unroll
          for (int w = 4; w < 12; w++) { T.xw[w] = psum(w >> 2, w & 3); T.accum(w, false); }
          asm volatile("" : "+r"(T.s1[0]), "+r"(T.s1[1]), "+r"(T.s2[0]), "+r"(T.s2[1]));
          if (!__any_sync(~0u, pbad(1, pbad(2, 0)) & 1)) break;
          if (++it > SPIN_LIMIT) SPIN_FAIL(__LINE__)
          pload(1);
        }
        #pragma unroll
        for (int w = 4; w < 12; w++) R.xw[w] = T.xw[w];
        R.s1[0] = T.s1[0]; R.s1[1] = T.s1[1]; R.s2[0] = T.s2[0]; R.s2[1] = T.s2[1];
      }
      STAMP(wg, layer * 16 + 10);
      if (layer == 0) {
        R.finish(scr, 3 + hf, warp, lane, 1.0f);
        R.gate_emit(scr, 3 + hf, warp, lane, pA, pM, 0);
      } else {
        store_out(0); store_out(1); store_out(2);
        op += 96 + warp * 8 + (ln >> 4) * 4 + (ln & 3);
        op[0] = R.xw[12]; op[D_ / 2] = R.xw[13];
      }
      STAMP(wg, layer * 16 + 11);
    }
  } else {
    auto load_w = [&](int ph, int c, int f) {
      const uint32_t dst = sb + c * SLOT, bar = bar_full + (c >> 1) * 8;
      mbar_expect_tx_e(bar, SLOT);
      if ((ph & 1) == 0) {
        tma3d(dst, &mp.w1a, 0, kchunk(c) * 64, (f * 224 + rank * 32) >> 6, bar);
        tma2d(dst + 24576, &mp.w1b, f * 224 + (rank ? 0 : 192), kchunk(c) * 64, bar);
      } else if (c > 0) {
        const int s = f ^ ((c - 1) & 1), col = (rank * 4 + ((c - 1) >> 1)) * 64;
        tma2d(dst, &mp.w2a, col, s * 224 + (s & 1) * 32, bar);
        tma2d(dst + 24576, &mp.w2b, col, s * 224 + ((s & 1) ? 0 : 192), bar);
      } else {
        #pragma unroll
        for (int u = 0; u < 2; u++) {
          const int s = f ^ u;
          tma2d(dst + u * HSLOT, &mp.w2c, 192 + rank * 32, s * 224 + (s & 1) * 32, bar);
          tma2d(dst + u * HSLOT + 12288, &mp.w2d, 192 + rank * 32, s * 224 + ((s & 1) ? 0 : 192), bar);
        }
      }
    };
    asm volatile("setmaxnreg.dec.sync.aligned.u32 24;");
    WARP
    const int lane = lane_id();
    const uint32_t t0 = clock32();
    if (lane == 0) {
      if (warp == 0) {
        #pragma unroll
        for (int i = 0; i < 7; i++) { mbar_init(bar_full + i * 8, i < 3 ? 2 : i == 3 ? 1 : 4); mbar_init(bar_empty + i * 8, 8); }
        mbar_init(bar_xr, 1); mbar_init(bar_xr + 8, 1); mbar_init(bar_cd, 8); mbar_init(bar_cd + 16, 8); mbar_init(bar_hk + 16, 1);
      } else {
        #pragma unroll
        for (int i = 0; i < 13; i++) mbar_init(bar_hf + (warp - 1) * 104 + i * 8, 1);
        if (sb != smem_u32(sm)) __trap();
      }
    }
    asm volatile("fence.mbarrier_init.release.cluster;" ::: "memory");
    bar_sync(5, 128);
    asm volatile("barrier.cluster.arrive.relaxed.aligned;" ::: "memory");
    ROLE
    if (warp == 0) {
      bar_arrive(7, 384);
      asm volatile("barrier.cluster.wait.aligned;" ::: "memory");
      {
        #pragma unroll
        for (int i = 0; i < 7; i++) asm volatile("prefetch.tensormap [%0];" :: "l"(&mp.w1a + i) : "memory");
        if (conv) {
          wait_clock(t0 + HDELAY);
          mbar_expect_tx_e(bar_hk, 4 * 4080);
          #pragma unroll
          for (int i = 0; i < 4; i++) bulk_g2s(sb + CV_H + i * H_PITCH + H_PAD + 16, hin + (cb * 4 + i) * 4096 + 16, 4080, bar_hk);
        }
        wait_clock(t0 + PQDELAY);
        pf((const uint8_t*)q + (r * 8 + f) * 7168, 7168); pf((const uint8_t*)q + (128 + r * 8 + f) * 7168, 7168);
        wait_clock(t0 + PWDELAY);
        pf(w1 + cb * 12544, 12544);
        wait_clock(t0 + QDELAY);
        mbar_expect_tx_e(bar_xr, 7168); mbar_expect_tx_e(bar_xr + 8, 7168);
        tma3d(sb + CV_Q, &mp.q, 0, (r * 8 + f) * 8, 0, bar_xr); tma3d(sb + CV_Q + 8192, &mp.q, 0, (128 + r * 8 + f) * 8, 0, bar_xr + 8);
        wait_clock(t0 + PVDELAY);
        pf(w2 + cb * 12544, 12544);
        #pragma unroll 1
        for (int c = 0; c < 4; c++) { wait_clock(t0 + WDELAY + c * WSPACE); load_w(0, c, f); }
        mbar_wait(bar_cd + 16, 0);
        load_w(0, 4, f); load_w(0, 5, f);
        mbar_wait(bar_cd, 0);
        load_w(0, 6, f);
        if (lane < 4) mbar_arrive_remote(mapa(bar_he, rank ^ 1) + lane * 8);
        __syncwarp();
        uint32_t tb = 0;
        #pragma unroll 1
        for (int ph = 1; ph < 4; ph++) {
          #pragma unroll 1
          for (int c = 0; c < 7; c++) {
            mbar_wait(bar_empty + c * 8, (ph - 1) & 1);
            if (ph == 2) {
              if (c == 0) tb = clock32();
              if (c >= WN) wait_clock(tb + WT + (c - WN) * WGAP);
            }
            load_w(ph, c, f);
          }
        }
      }
    } else if (warp == 3) {
      STAMP(2, 0);
      const uint32_t* hk = g_HK + min(cb >> 4, 6) * 32;
      uint32_t ln = ld_rlx32(g_HY + (lane & never));
      const uint32_t v0 = ld_rlx32(hk + (lane & never));
      bar_arrive(7, 384);
      ln = launch_no(ln);
      const uint32_t tk = (int)((v0 - ln * 16) << 3) < 0 ? poll_hint(hk, ln * 16) : clock32();
      STAMP(2, 2);
      wait_clock(tk + KLEAD);
      STAMP(2, 3);
      if (lane == 0) mbar_arrive(bar_hk + 16);
      asm volatile("barrier.cluster.wait.aligned;" ::: "memory");
      const uint32_t ty = poll_hint(g_HY, ln * 128);
      STAMP(2, 4);
      wait_clock(ty + YALEAD);
      if (lane == 0) mbar_arrive(bar_go + 64);
      wait_clock(ty + X0LEADA);
      if (lane == 0) mbar_arrive(bar_go);
      wait_clock(ty + YBLEAD);
      if (lane == 0) mbar_arrive(bar_go + 72);
      wait_clock(ty + YBLEAD + X0LEADB);
      if (lane == 0) mbar_arrive(bar_go + 32);
    } else {
      const int hf = warp - 1;
      if (hf && conv) {
        const uint32_t dvr = __ldg((const uint16_t*)dvec + cb * 4 + (lane >> 3));
        uint32_t hw = __ldg((const uint32_t*)(hin + (cb * 4 + (lane >> 3)) * 4096) + (lane & 3));
        #pragma unroll
        for (int i = 0; i < 6; i++) sts64(sb + CV_H + (lane >> 3) * H_PITCH + (lane & 7) * 8 + i * 64, 0, 0);
        if ((lane & 3) == 0) hw = pack2(bf_lo(hw) + bf_lo(dvr), bf_hi(hw));
        sts32(sb + CV_H + (lane >> 3) * H_PITCH + H_PAD + (lane & 3) * 4, hw);
        fence_async();
      }
      uint32_t* const fl = g_FL + (r * 2 + hf) * 32;
      const uint32_t f0 = ld_rlx32(fl + (lane & never));
      bar_arrive(7, 384);
      asm volatile("barrier.cluster.wait.aligned;" ::: "memory");
      if (!hf) {
        bar_sync(13, 288);
        if (lane == 0) post_hint(g_HY, sb + SM_RED, never);
        __syncwarp();
      }
      #pragma unroll 1
      for (int layer = 0; layer < 2; layer++) {
        mbar_wait(bar_full + 32 + hf * 8, layer);
        if (lane == 0) post_hint(fl, sb + SM_RED, never);
        const uint32_t tp = poll_hint(fl, (f0 & ~7u) + 8 + 8 * layer);
        wait_clock(tp + (layer ? PLEAD2 : hf ? PLEADB : PLEADA));
        if (lane == 0) mbar_arrive(bar_go + (hf * 4 + layer * 2 + 1) * 8);
        if (layer == 0) {
          wait_clock(tp + (hf ? XLEADB : XLEADA));
          if (lane == 0) mbar_arrive(bar_go + (hf * 4 + 2) * 8);
        }
      }
    }
  }
}

typedef CUresult (*EncodeFn)(CUtensorMap*, CUtensorMapDataType, cuuint32_t, void*, const cuuint64_t*, const cuuint64_t*, const cuuint32_t*, const cuuint32_t*,
                             CUtensorMapInterleave, CUtensorMapSwizzle, CUtensorMapL2promotion, CUtensorMapFloatOOBfill);

}

extern "C" void kernel_launch(void* const* d_in, const int* in_sizes, int n_in, void* d_out, int out_size) {
  const __nv_bfloat16* q = (const __nv_bfloat16*)d_in[0];
  const __nv_bfloat16* k = (const __nv_bfloat16*)d_in[1];
  const __nv_bfloat16* v = (const __nv_bfloat16*)d_in[2];
  const __nv_bfloat16* sk = (const __nv_bfloat16*)d_in[3];
  const __nv_bfloat16* h = (const __nv_bfloat16*)d_in[4];
  const __nv_bfloat16* Dv = (const __nv_bfloat16*)d_in[5];
  void* w1 = d_in[7];
  void* w2 = d_in[8];
  void* fn = nullptr;
  cudaDriverEntryPointQueryResult qr;
  cudaGetDriverEntryPoint("cuTensorMapEncodeTiled", &fn, cudaEnableDefault, &qr);
  EncodeFn enc = (EncodeFn)fn;
  Maps mp;
  const cuuint32_t es[3] = {1, 1, 1};
  auto enc2 = [&](CUtensorMap* m, void* base, int d0, int d1, int b0, int b1) {
    cuuint64_t gd[2] = {(cuuint64_t)d0, (cuuint64_t)d1}; cuuint64_t gs[1] = {(cuuint64_t)d0 * 2}; cuuint32_t bx[2] = {(cuuint32_t)b0, (cuuint32_t)b1};
    enc(m, CU_TENSOR_MAP_DATA_TYPE_BFLOAT16, 2, base, gd, gs, bx, es, CU_TENSOR_MAP_INTERLEAVE_NONE,
        b0 == 64 ? CU_TENSOR_MAP_SWIZZLE_128B : CU_TENSOR_MAP_SWIZZLE_64B, CU_TENSOR_MAP_L2_PROMOTION_L2_128B, CU_TENSOR_MAP_FLOAT_OOB_FILL_NONE);
  };
  auto enc3 = [&](CUtensorMap* m, const void* base, int cols, int rows, int b1, int b2) {
    cuuint64_t gd[3] = {64, (cuuint64_t)rows, (cuuint64_t)cols / 64}; cuuint64_t gs[2] = {(cuuint64_t)cols * 2, 128}; cuuint32_t bx[3] = {64, (cuuint32_t)b1, (cuuint32_t)b2};
    enc(m, CU_TENSOR_MAP_DATA_TYPE_BFLOAT16, 3, (void*)base, gd, gs, bx, es, CU_TENSOR_MAP_INTERLEAVE_NONE, CU_TENSOR_MAP_SWIZZLE_128B, CU_TENSOR_MAP_L2_PROMOTION_L2_128B, CU_TENSOR_MAP_FLOAT_OOB_FILL_NONE);
  };
  enc3(&mp.w1a, w1, F_, D_, 64, 3);
  enc3(&mp.q, q, D_, S_, 8, 7);
  enc2(&mp.w1b, w1, F_, D_, 32, 64);
  enc2(&mp.w2a, w2, D_, F_, 64, 192); enc2(&mp.w2b, w2, D_, F_, 64, 32);
  enc2(&mp.w2c, w2, D_, F_, 32, 192); enc2(&mp.w2d, w2, D_, F_, 32, 32);
  for (int cl = 0; cl < 64; cl++) {
    int pc, r;
    if (cl < 4) { pc = 0; r = 12 + cl; }
    else if (cl < 36) { const int i = (cl - 4) & 7; pc = i >> 1; r = (i & 1) * 4 + ((cl - 4) >> 3); }
    else { const int j = (cl - 36) % 7; pc = (j + 1) >> 1; r = 8 + (j ? ((j + 1) & 1) * 4 : 0) + (cl - 36) / 7; }
    mp.role[cl] = pc * 16 + r;
  }
  cudaFuncSetAttribute(k_main, cudaFuncAttributeMaxDynamicSharedMemorySize, SM_TOTAL);
  void* gs = nullptr;
  cudaGetSymbolAddress(&gs, g_scratch);
  k_main<<<128, 384, SM_TOTAL>>>((const uint8_t*)k, (const uint8_t*)v, (uint8_t*)gs, (const uint2*)sk, (const uint8_t*)h, 0, q, Dv,
                                 (const uint8_t*)w1, (const uint8_t*)w2, (__nv_bfloat16*)d_out, mp);
}
```
